```python
import torch

def _softmax(x, axis=-1):
    return torch.softmax(x, dim=axis)
def _gelu(x):
    return torch.nn.functional.gelu(x, approximate="tanh")
def _silu(x):
    return torch.nn.functional.silu(x)
def _sigmoid(x):
    return torch.sigmoid(x)
def _layernorm(x, axis=-1, eps=1e-5):
    m = x.mean(dim=axis, keepdim=True)
    v = x.var(dim=axis, keepdim=True, unbiased=False)
    return (x - m) / torch.sqrt(v + eps)
def _scatter_add(tgt, idx, src, axis=0):
    return tgt.clone().index_add_(axis, idx, src)
def _segment_sum(src, seg, n):
    out = torch.zeros((n,) + src.shape[1:], dtype=src.dtype)
    return out.index_add_(0, seg, src)
def _pad(x, pw):
    flat = tuple(v for pair in reversed(pw) for v in pair)
    return torch.nn.functional.pad(x, flat)

kernel_name = 'concat_heads__sliding_block__linear_attn_block__prompt'

def setup_inputs():

    _w = (lambda a: (lambda t: t.to(torch.bfloat16) if t.is_floating_point() else t)(torch.as_tensor(a)))
    def _A_setup():
        B, S, D = 1, 2048, 576
        return {
            "x": _w((lambda *s: torch.randn(*s, dtype=torch.bfloat16) * 0.2)(B, S, D)),
            "wqkv": _w((lambda *s: torch.randn(*s, dtype=torch.bfloat16) * 0.2)(D, 3 * D)),
            "wo": _w((lambda *s: torch.randn(*s, dtype=torch.bfloat16) * 0.05)(D, D)),
        }
    _A_in = _A_setup()

    def _B_setup():
        B, S, D = 1, 2048, 576
        return {
            "x": _w((lambda *s: torch.randn(*s, dtype=torch.bfloat16) * 0.05)(B, S, D)),
            "wqkv": _w((lambda *s: torch.randn(*s, dtype=torch.bfloat16) * 0.8)(D, 3 * D)),
            "wo": _w((lambda *s: torch.randn(*s, dtype=torch.bfloat16) * 0.8)(D, D)),
        }
    _B_in = _B_setup()

    return {
        "A_x": _A_in["x"],
        "A_wqkv": _A_in["wqkv"],
        "A_wo": _A_in["wo"],
        "B_x": _B_in["x"],
        "B_wqkv": _B_in["wqkv"],
        "B_wo": _B_in["wo"],
    }

def reference(A_x, A_wqkv, A_wo, B_x, B_wqkv, B_wo):
    def _A_ref(x, wqkv, wo):
        B, S, D = x.shape
        H = 32; Dh = D // H; W = 256
        qkv = (lambda x, *d: x.permute(*d))((x @ wqkv).reshape(B, S, 3, H, Dh), 2, 0, 3, 1, 4)
        q, k, v = qkv[0], qkv[1], qkv[2]
        scores = torch.einsum("bhqd,bhkd->bhqk", q, k) * (Dh ** -0.5)
        idx = torch.arange(S)
        mask = (idx[:, None] - idx[None, :] >= 0) & (idx[:, None] - idx[None, :] < W)
        scores = torch.where(mask[None, None], scores, -1e9)
        p = _softmax(scores, axis=-1)
        o = torch.einsum("bhqk,bhkd->bhqd", p, v)
        return (lambda x, *d: x.permute(*d))(o, 0, 2, 1, 3).reshape(B, S, D) @ wo

    def _B_ref(x, wqkv, wo):
        B, S, D = x.shape
        H = 32; Dh = D // H
        qkv = (lambda x, *d: x.permute(*d))((x @ wqkv).reshape(B, S, 3, H, Dh), 2, 0, 3, 1, 4)
        q, k, v = qkv[0], qkv[1], qkv[2]
        phi = lambda t: torch.where(t > 0, t + 1, torch.exp(t)) + 1e-6
        pq, pk = phi(q), phi(k)
        kv = torch.einsum("bhsd,bhse->bhde", pk, v)
        z = torch.einsum("bhsd->bhd", pk)
        num = torch.einsum("bhqd,bhde->bhqe", pq, kv)
        den = torch.einsum("bhqd,bhd->bhq", pq, z)[..., None] + 1e-6
        o = num / den
        return (lambda x, *d: x.permute(*d))(o, 0, 2, 1, 3).reshape(B, S, D) @ wo

    a = _A_ref(A_x, A_wqkv, A_wo)
    b = _B_ref(B_x, B_wqkv, B_wo)
    return torch.concatenate([a, b], axis=-1)
```

```cpp
#include <cuda_runtime.h>
#include <cuda.h>
#include <cuda_bf16.h>
#include <stdint.h>

namespace {

constexpr int SEQ = 2048;
constexpr int NCTA = 128;
constexpr int NTHREADS = 384;
#define ATT_UNROLL 3
#define ATT_STR2(x) #x
#define ATT_STR(x) ATT_STR2(x)
#define ATT_PRAGMA ATT_STR(unroll ATT_UNROLL)
#define PERM_GAP 0
#define AST_GAP 400

constexpr int STAGE_BYTES = 49152;
constexpr int NSTAGE = 3;
constexpr int SM_KV = NSTAGE * STAGE_BYTES;
constexpr int KV_CHUNK = 768 * 16;
constexpr int SM_BAR = SM_KV + 6 * KV_CHUNK;
constexpr int SM_TOTAL = SM_BAR + 512 + 5760;
constexpr int SMEM_BYTES = SM_TOTAL + 1024;
constexpr int SM_ONES0 = SM_KV - 72192;
constexpr int SM_V = SM_ONES0 + 2048;
constexpr int SM_ONES1 = SM_V + 18432;
constexpr int SM_PK = SM_ONES1 + 2048;
constexpr int SM_PQ = SM_PK + 18432;
constexpr int SM_KVMAT = SM_PQ + 18432;
static_assert(SM_KVMAT + 12800 == SM_KV, "smem");
constexpr int SM_KVP = SM_BAR + 512;
constexpr int WO_STAGE = 16384 + 18432;
constexpr int WO_NSTAGE = 4;
static_assert(WO_NSTAGE * WO_STAGE <= SM_KV && 2 * WO_STAGE <= SM_ONES0, "smem");

enum {
  B_FULL = 0,
  B_EMPTY = 4,
  B_FULL3 = 8,
  B_EMPTY3 = 12,
  B_STGA = 16,
  B_KV = 18,
  B_KV2 = 19,
  B_UNUSED = 20,
  B_BLOADS = 21,
  B_OA = 22,
  B_EPOCH = 23,
  B_BST = 24,
  B_P2DONE = 25,
  B_ADEP = 26,
  B_COUNT = 27
};
constexpr int SM_MISC = SM_BAR + 8 * B_COUNT;

enum { C_TICKET = 0, C_W = 1, C_A = 2, C_KV = 18, C_W2 = 26, C_OA = 27, C_OB = 27 + 144, C_COUNT = 27 + 288 };

__device__ __align__(1024) __nv_bfloat16 g_qkvA[216 * SEQ * 8];
__device__ __align__(1024) __nv_bfloat16 g_wBp[216 * 576 * 8];
__device__ __align__(1024) __nv_bfloat16 g_oA[72 * SEQ * 8];
__device__ __align__(1024) __nv_bfloat16 g_oB[72 * SEQ * 8];
__device__ __align__(1024) __nv_bfloat16 g_woP[2 * 72 * 576 * 8];
__device__ __align__(1024) float g_kvsum[8 * 72 * 20];
__device__ __align__(1024) unsigned g_cnt[C_COUNT * 32];
#define TL(slot) do { } while (0)
#define TC(slot) do { } while (0)
#define TX(slot) do { } while (0)

struct Params {
  CUtensorMap xA, xB;
  CUtensorMap wA3, wA1;
  CUtensorMap wB;
  CUtensorMap st4;
  CUtensorMap kvA;
  CUtensorMap oA, oB;
  CUtensorMap wo;
  CUtensorMap out;
  const __nv_bfloat16* woA;
  const __nv_bfloat16* woB;
  const __nv_bfloat16* wBsrc;
  const __nv_bfloat16* xAsrc;
  const __nv_bfloat16* wAsrc;
};

__device__ __forceinline__ uint32_t smem_u32(const void* p) { return (uint32_t)__cvta_generic_to_shared(p); }
__device__ __forceinline__ unsigned long long gtimer() { unsigned long long t; asm volatile("mov.u64 %0, %%globaltimer;" : "=l"(t)); return t; }
__device__ __forceinline__ int fresh_cta() { int v; asm volatile("mov.u32 %0, %%ctaid.x;" : "=r"(v)); return v; }
__device__ __forceinline__ int fresh_tid() { int v; asm volatile("mov.u32 %0, %%tid.x;" : "=r"(v)); return v; }
__device__ __forceinline__ void pace(int cycles) {
  const long long t0 = clock64();
  while (clock64() - t0 < cycles) {}
}
__device__ __forceinline__ void mbar_init(uint32_t bar, uint32_t cnt) { asm volatile("mbarrier.init.shared::cta.b64 [%0], %1;" ::"r"(bar), "r"(cnt) : "memory"); }
__device__ __forceinline__ void mbar_expect_tx(uint32_t bar, uint32_t bytes) { asm volatile("mbarrier.arrive.expect_tx.shared::cta.b64 _, [%0], %1;" ::"r"(bar), "r"(bytes) : "memory"); }
__device__ __forceinline__ void mbar_arrive(uint32_t bar) { asm volatile("mbarrier.arrive.shared::cta.b64 _, [%0];" ::"r"(bar) : "memory"); }
__device__ __forceinline__ void mbar_wait(uint32_t bar, uint32_t parity) {
  uint32_t ok;
  int spins = 0;
  do {
    asm volatile("{\n.reg .pred p;\nmbarrier.try_wait.parity.shared::cta.b64 p, [%1], %2;\nselp.u32 %0, 1, 0, p;\n}" : "=r"(ok) : "r"(bar), "r"(parity) : "memory");
  } while (!ok && ++spins < (1 << 20));
}
__device__ __forceinline__ bool mbar_test(uint32_t bar, uint32_t parity) {
  uint32_t ok;
  asm volatile("{\n.reg .pred p;\nmbarrier.test_wait.parity.shared::cta.b64 p, [%1], %2;\nselp.u32 %0, 1, 0, p;\n}" : "=r"(ok) : "r"(bar), "r"(parity) : "memory");
  return ok != 0;
}
__device__ __forceinline__ void tma_load_2d(uint32_t dst, const CUtensorMap* m, uint32_t bar, int c0, int c1) {
  asm volatile("cp.async.bulk.tensor.2d.shared::cluster.global.mbarrier::complete_tx::bytes [%0], [%1, {%3, %4}], [%2];"
               ::"r"(dst), "l"(m), "r"(bar), "r"(c0), "r"(c1) : "memory");
}
__device__ __forceinline__ void tma_load_3d(uint32_t dst, const CUtensorMap* m, uint32_t bar, int c0, int c1, int c2) {
  asm volatile("cp.async.bulk.tensor.3d.shared::cluster.global.mbarrier::complete_tx::bytes [%0], [%1, {%3, %4, %5}], [%2];"
               ::"r"(dst), "l"(m), "r"(bar), "r"(c0), "r"(c1), "r"(c2) : "memory");
}
__device__ __forceinline__ void tma_store_2d(const CUtensorMap* m, uint32_t src, int c0, int c1) {
  asm volatile("cp.async.bulk.tensor.2d.global.shared::cta.bulk_group [%0, {%2, %3}], [%1];" ::"l"(m), "r"(src), "r"(c0), "r"(c1) : "memory");
}
__device__ __forceinline__ void tma_store_3d(const CUtensorMap* m, uint32_t src, int c0, int c1, int c2) {
  asm volatile("cp.async.bulk.tensor.3d.global.shared::cta.bulk_group [%0, {%2, %3, %4}], [%1];" ::"l"(m), "r"(src), "r"(c0), "r"(c1), "r"(c2) : "memory");
}
__device__ __forceinline__ void bulk_commit() { asm volatile("cp.async.bulk.commit_group;" ::: "memory"); }
__device__ __forceinline__ void bulk_wait_all() { asm volatile("cp.async.bulk.wait_group 0;" ::: "memory"); }
__device__ __forceinline__ void bulk_wait_read() { asm volatile("cp.async.bulk.wait_group.read 0;" ::: "memory"); }
__device__ __forceinline__ void fence_async_smem() { asm volatile("fence.proxy.async.shared::cta;" ::: "memory"); }
__device__ __forceinline__ void fence_async_glb() { asm volatile("fence.proxy.async.global;" ::: "memory"); }
__device__ __forceinline__ void fence_gpu() { asm volatile("fence.acq_rel.gpu;" ::: "memory"); }
__device__ __forceinline__ void prefetch_map(const CUtensorMap* m) { asm volatile("prefetch.tensormap [%0];" ::"l"(m) : "memory"); }
__device__ __forceinline__ void named_bar(int id, int n) { asm volatile("bar.sync %0, %1;" ::"r"(id), "r"(n) : "memory"); }

__device__ __forceinline__ void cnt_signal(int idx) {
  fence_gpu();
  asm volatile("red.relaxed.gpu.global.add.u32 [%0], 1;" ::"l"(&g_cnt[idx * 32]) : "memory");
}
__device__ __forceinline__ void cnt_signal_nofence(int idx) {
  asm volatile("red.relaxed.gpu.global.add.u32 [%0], 1;" ::"l"(&g_cnt[idx * 32]) : "memory");
}
__device__ __forceinline__ unsigned ld_relaxed(const unsigned* p) {
  unsigned v;
  asm volatile("ld.relaxed.gpu.global.u32 %0, [%1];" : "=r"(v) : "l"(p) : "memory");
  return v;
}
__device__ __forceinline__ unsigned ld_acquire(const unsigned* p) {
  unsigned v;
  asm volatile("ld.acquire.gpu.global.u32 %0, [%1];" : "=r"(v) : "l"(p) : "memory");
  return v;
}
__device__ __forceinline__ void cnt_wait(int idx, unsigned target) {
  int spins = 0;
  while ((int)(ld_relaxed(&g_cnt[idx * 32]) - target) < 0 && ++spins < (1 << 20)) {}
  (void)ld_acquire(&g_cnt[idx * 32]);
}
__device__ __forceinline__ void cnt_wait_warp(int idx, unsigned target, bool use) {
  int spins = 0;
  bool ok;
  do {
    ok = !use || (int)(ld_acquire(&g_cnt[idx * 32]) - target) >= 0;
  } while (!__all_sync(0xffffffffu, ok) && ++spins < (1 << 20));
}

__device__ __forceinline__ uint64_t make_desc(uint32_t addr, uint32_t lbo, uint32_t sbo, uint32_t swz) {
  uint64_t d = 0;
  d |= (uint64_t)((addr & 0x3FFFF) >> 4);
  d |= (uint64_t)((lbo & 0x3FFFF) >> 4) << 16;
  d |= (uint64_t)((sbo & 0x3FFFF) >> 4) << 32;
  d |= (uint64_t)swz << 62;
  return d;
}
__device__ __forceinline__ void wg_fence() { asm volatile("wgmma.fence.sync.aligned;" ::: "memory"); }
__device__ __forceinline__ void wg_commit() { asm volatile("wgmma.commit_group.sync.aligned;" ::: "memory"); }
template <int N> __device__ __forceinline__ void wg_wait() { asm volatile("wgmma.wait_group.sync.aligned %0;" ::"n"(N) : "memory"); }
template <int N> __device__ __forceinline__ void fence_regs(float* d) {
#pragma unroll
  for (int i = 0; i < N; i++) asm volatile("" : "+f"(d[i])::"memory");
}
template <int N> __device__ __forceinline__ void fence_regs_u(uint32_t* d) {
#pragma unroll
  for (int i = 0; i < N; i++) asm volatile("" : "+r"(d[i])::"memory");
}
__device__ __forceinline__ uint32_t pack_bf16(float lo, float hi) {
  uint32_t r;
  asm("cvt.rn.bf16x2.f32 %0, %1, %2;" : "=r"(r) : "f"(hi), "f"(lo));
  return r;
}
__device__ __forceinline__ float ex2(float x) { float y; asm("ex2.approx.ftz.f32 %0, %1;" : "=f"(y) : "f"(x)); return y; }
__device__ __forceinline__ float rcp_fast(float x) { float y; asm("rcp.approx.ftz.f32 %0, %1;" : "=f"(y) : "f"(x)); return y; }
__device__ __forceinline__ void stmatrix_x4(uint32_t addr, uint32_t r0, uint32_t r1, uint32_t r2, uint32_t r3) {
  asm volatile("stmatrix.sync.aligned.m8n8.x4.shared.b16 [%0], {%1, %2, %3, %4};" ::"r"(addr), "r"(r0), "r"(r1), "r"(r2), "r"(r3) : "memory");
}

__device__ __forceinline__ void wgmma_ss_n256_a0_b1(float* d, uint64_t da, uint64_t db, int scale_d) {
  asm volatile("{\n.reg .pred p;\nsetp.ne.b32 p, %130, 0;\n"
    "wgmma.mma_async.sync.aligned.m64n256k16.f32.bf16.bf16 "
    "{%0,%1,%2,%3,%4,%5,%6,%7,%8,%9,%10,%11,%12,%13,%14,%15,%16,%17,%18,%19,%20,%21,%22,%23,%24,%25,%26,%27,%28,%29,%30,%31,%32,%33,%34,%35,%36,%37,%38,%39,%40,%41,%42,%43,%44,%45,%46,%47,%48,%49,%50,%51,%52,%53,%54,%55,%56,%57,%58,%59,%60,%61,%62,%63,%64,%65,%66,%67,%68,%69,%70,%71,%72,%73,%74,%75,%76,%77,%78,%79,%80,%81,%82,%83,%84,%85,%86,%87,%88,%89,%90,%91,%92,%93,%94,%95,%96,%97,%98,%99,%100,%101,%102,%103,%104,%105,%106,%107,%108,%109,%110,%111,%112,%113,%114,%115,%116,%117,%118,%119,%120,%121,%122,%123,%124,%125,%126,%127}, %128, %129, p, 1, 1, 0, 1;\n}\n"
    : "+f"(d[0]), "+f"(d[1]), "+f"(d[2]), "+f"(d[3]), "+f"(d[4]), "+f"(d[5]), "+f"(d[6]), "+f"(d[7]),
      "+f"(d[8]), "+f"(d[9]), "+f"(d[10]), "+f"(d[11]), "+f"(d[12]), "+f"(d[13]), "+f"(d[14]), "+f"(d[15]),
      "+f"(d[16]), "+f"(d[17]), "+f"(d[18]), "+f"(d[19]), "+f"(d[20]), "+f"(d[21]), "+f"(d[22]), "+f"(d[23]),
      "+f"(d[24]), "+f"(d[25]), "+f"(d[26]), "+f"(d[27]), "+f"(d[28]), "+f"(d[29]), "+f"(d[30]), "+f"(d[31]),
      "+f"(d[32]), "+f"(d[33]), "+f"(d[34]), "+f"(d[35]), "+f"(d[36]), "+f"(d[37]), "+f"(d[38]), "+f"(d[39]),
      "+f"(d[40]), "+f"(d[41]), "+f"(d[42]), "+f"(d[43]), "+f"(d[44]), "+f"(d[45]), "+f"(d[46]), "+f"(d[47]),
      "+f"(d[48]), "+f"(d[49]), "+f"(d[50]), "+f"(d[51]), "+f"(d[52]), "+f"(d[53]), "+f"(d[54]), "+f"(d[55]),
      "+f"(d[56]), "+f"(d[57]), "+f"(d[58]), "+f"(d[59]), "+f"(d[60]), "+f"(d[61]), "+f"(d[62]), "+f"(d[63]),
      "+f"(d[64]), "+f"(d[65]), "+f"(d[66]), "+f"(d[67]), "+f"(d[68]), "+f"(d[69]), "+f"(d[70]), "+f"(d[71]),
      "+f"(d[72]), "+f"(d[73]), "+f"(d[74]), "+f"(d[75]), "+f"(d[76]), "+f"(d[77]), "+f"(d[78]), "+f"(d[79]),
      "+f"(d[80]), "+f"(d[81]), "+f"(d[82]), "+f"(d[83]), "+f"(d[84]), "+f"(d[85]), "+f"(d[86]), "+f"(d[87]),
      "+f"(d[88]), "+f"(d[89]), "+f"(d[90]), "+f"(d[91]), "+f"(d[92]), "+f"(d[93]), "+f"(d[94]), "+f"(d[95]),
      "+f"(d[96]), "+f"(d[97]), "+f"(d[98]), "+f"(d[99]), "+f"(d[100]), "+f"(d[101]), "+f"(d[102]), "+f"(d[103]),
      "+f"(d[104]), "+f"(d[105]), "+f"(d[106]), "+f"(d[107]), "+f"(d[108]), "+f"(d[109]), "+f"(d[110]), "+f"(d[111]),
      "+f"(d[112]), "+f"(d[113]), "+f"(d[114]), "+f"(d[115]), "+f"(d[116]), "+f"(d[117]), "+f"(d[118]), "+f"(d[119]),
      "+f"(d[120]), "+f"(d[121]), "+f"(d[122]), "+f"(d[123]), "+f"(d[124]), "+f"(d[125]), "+f"(d[126]), "+f"(d[127])
    : "l"(da), "l"(db), "r"(scale_d));
}

__device__ __forceinline__ void wgmma_ss_n192_a0_b1(float* d, uint64_t da, uint64_t db, int scale_d) {
  asm volatile("{\n.reg .pred p;\nsetp.ne.b32 p, %98, 0;\n"
    "wgmma.mma_async.sync.aligned.m64n192k16.f32.bf16.bf16 "
    "{%0,%1,%2,%3,%4,%5,%6,%7,%8,%9,%10,%11,%12,%13,%14,%15,%16,%17,%18,%19,%20,%21,%22,%23,%24,%25,%26,%27,%28,%29,%30,%31,%32,%33,%34,%35,%36,%37,%38,%39,%40,%41,%42,%43,%44,%45,%46,%47,%48,%49,%50,%51,%52,%53,%54,%55,%56,%57,%58,%59,%60,%61,%62,%63,%64,%65,%66,%67,%68,%69,%70,%71,%72,%73,%74,%75,%76,%77,%78,%79,%80,%81,%82,%83,%84,%85,%86,%87,%88,%89,%90,%91,%92,%93,%94,%95}, %96, %97, p, 1, 1, 0, 1;\n}\n"
    : "+f"(d[0]), "+f"(d[1]), "+f"(d[2]), "+f"(d[3]), "+f"(d[4]), "+f"(d[5]), "+f"(d[6]), "+f"(d[7]),
      "+f"(d[8]), "+f"(d[9]), "+f"(d[10]), "+f"(d[11]), "+f"(d[12]), "+f"(d[13]), "+f"(d[14]), "+f"(d[15]),
      "+f"(d[16]), "+f"(d[17]), "+f"(d[18]), "+f"(d[19]), "+f"(d[20]), "+f"(d[21]), "+f"(d[22]), "+f"(d[23]),
      "+f"(d[24]), "+f"(d[25]), "+f"(d[26]), "+f"(d[27]), "+f"(d[28]), "+f"(d[29]), "+f"(d[30]), "+f"(d[31]),
      "+f"(d[32]), "+f"(d[33]), "+f"(d[34]), "+f"(d[35]), "+f"(d[36]), "+f"(d[37]), "+f"(d[38]), "+f"(d[39]),
      "+f"(d[40]), "+f"(d[41]), "+f"(d[42]), "+f"(d[43]), "+f"(d[44]), "+f"(d[45]), "+f"(d[46]), "+f"(d[47]),
      "+f"(d[48]), "+f"(d[49]), "+f"(d[50]), "+f"(d[51]), "+f"(d[52]), "+f"(d[53]), "+f"(d[54]), "+f"(d[55]),
      "+f"(d[56]), "+f"(d[57]), "+f"(d[58]), "+f"(d[59]), "+f"(d[60]), "+f"(d[61]), "+f"(d[62]), "+f"(d[63]),
      "+f"(d[64]), "+f"(d[65]), "+f"(d[66]), "+f"(d[67]), "+f"(d[68]), "+f"(d[69]), "+f"(d[70]), "+f"(d[71]),
      "+f"(d[72]), "+f"(d[73]), "+f"(d[74]), "+f"(d[75]), "+f"(d[76]), "+f"(d[77]), "+f"(d[78]), "+f"(d[79]),
      "+f"(d[80]), "+f"(d[81]), "+f"(d[82]), "+f"(d[83]), "+f"(d[84]), "+f"(d[85]), "+f"(d[86]), "+f"(d[87]),
      "+f"(d[88]), "+f"(d[89]), "+f"(d[90]), "+f"(d[91]), "+f"(d[92]), "+f"(d[93]), "+f"(d[94]), "+f"(d[95])
    : "l"(da), "l"(db), "r"(scale_d));
}

__device__ __forceinline__ void wgmma_ss_n216_a0_b1(float* d, uint64_t da, uint64_t db, int scale_d) {
  asm volatile("{\n.reg .pred p;\nsetp.ne.b32 p, %110, 0;\n"
    "wgmma.mma_async.sync.aligned.m64n216k16.f32.bf16.bf16 "
    "{%0,%1,%2,%3,%4,%5,%6,%7,%8,%9,%10,%11,%12,%13,%14,%15,%16,%17,%18,%19,%20,%21,%22,%23,%24,%25,%26,%27,%28,%29,%30,%31,%32,%33,%34,%35,%36,%37,%38,%39,%40,%41,%42,%43,%44,%45,%46,%47,%48,%49,%50,%51,%52,%53,%54,%55,%56,%57,%58,%59,%60,%61,%62,%63,%64,%65,%66,%67,%68,%69,%70,%71,%72,%73,%74,%75,%76,%77,%78,%79,%80,%81,%82,%83,%84,%85,%86,%87,%88,%89,%90,%91,%92,%93,%94,%95,%96,%97,%98,%99,%100,%101,%102,%103,%104,%105,%106,%107}, %108, %109, p, 1, 1, 0, 1;\n}\n"
    : "+f"(d[0]), "+f"(d[1]), "+f"(d[2]), "+f"(d[3]), "+f"(d[4]), "+f"(d[5]), "+f"(d[6]), "+f"(d[7]),
      "+f"(d[8]), "+f"(d[9]), "+f"(d[10]), "+f"(d[11]), "+f"(d[12]), "+f"(d[13]), "+f"(d[14]), "+f"(d[15]),
      "+f"(d[16]), "+f"(d[17]), "+f"(d[18]), "+f"(d[19]), "+f"(d[20]), "+f"(d[21]), "+f"(d[22]), "+f"(d[23]),
      "+f"(d[24]), "+f"(d[25]), "+f"(d[26]), "+f"(d[27]), "+f"(d[28]), "+f"(d[29]), "+f"(d[30]), "+f"(d[31]),
      "+f"(d[32]), "+f"(d[33]), "+f"(d[34]), "+f"(d[35]), "+f"(d[36]), "+f"(d[37]), "+f"(d[38]), "+f"(d[39]),
      "+f"(d[40]), "+f"(d[41]), "+f"(d[42]), "+f"(d[43]), "+f"(d[44]), "+f"(d[45]), "+f"(d[46]), "+f"(d[47]),
      "+f"(d[48]), "+f"(d[49]), "+f"(d[50]), "+f"(d[51]), "+f"(d[52]), "+f"(d[53]), "+f"(d[54]), "+f"(d[55]),
      "+f"(d[56]), "+f"(d[57]), "+f"(d[58]), "+f"(d[59]), "+f"(d[60]), "+f"(d[61]), "+f"(d[62]), "+f"(d[63]),
      "+f"(d[64]), "+f"(d[65]), "+f"(d[66]), "+f"(d[67]), "+f"(d[68]), "+f"(d[69]), "+f"(d[70]), "+f"(d[71]),
      "+f"(d[72]), "+f"(d[73]), "+f"(d[74]), "+f"(d[75]), "+f"(d[76]), "+f"(d[77]), "+f"(d[78]), "+f"(d[79]),
      "+f"(d[80]), "+f"(d[81]), "+f"(d[82]), "+f"(d[83]), "+f"(d[84]), "+f"(d[85]), "+f"(d[86]), "+f"(d[87]),
      "+f"(d[88]), "+f"(d[89]), "+f"(d[90]), "+f"(d[91]), "+f"(d[92]), "+f"(d[93]), "+f"(d[94]), "+f"(d[95]),
      "+f"(d[96]), "+f"(d[97]), "+f"(d[98]), "+f"(d[99]), "+f"(d[100]), "+f"(d[101]), "+f"(d[102]), "+f"(d[103]),
      "+f"(d[104]), "+f"(d[105]), "+f"(d[106]), "+f"(d[107])
    : "l"(da), "l"(db), "r"(scale_d));
}

__device__ __forceinline__ void wgmma_rs_n80_b0(float* d, uint32_t a0, uint32_t a1, uint32_t a2, uint32_t a3, uint64_t db, int scale_d) {
  asm volatile("{\n.reg .pred p;\nsetp.ne.b32 p, %45, 0;\n"
    "wgmma.mma_async.sync.aligned.m64n80k16.f32.bf16.bf16 "
    "{%0,%1,%2,%3,%4,%5,%6,%7,%8,%9,%10,%11,%12,%13,%14,%15,%16,%17,%18,%19,%20,%21,%22,%23,%24,%25,%26,%27,%28,%29,%30,%31,%32,%33,%34,%35,%36,%37,%38,%39}, {%40,%41,%42,%43}, %44, p, 1, 1, 0;\n}\n"
    : "+f"(d[0]), "+f"(d[1]), "+f"(d[2]), "+f"(d[3]), "+f"(d[4]), "+f"(d[5]), "+f"(d[6]), "+f"(d[7]),
      "+f"(d[8]), "+f"(d[9]), "+f"(d[10]), "+f"(d[11]), "+f"(d[12]), "+f"(d[13]), "+f"(d[14]), "+f"(d[15]),
      "+f"(d[16]), "+f"(d[17]), "+f"(d[18]), "+f"(d[19]), "+f"(d[20]), "+f"(d[21]), "+f"(d[22]), "+f"(d[23]),
      "+f"(d[24]), "+f"(d[25]), "+f"(d[26]), "+f"(d[27]), "+f"(d[28]), "+f"(d[29]), "+f"(d[30]), "+f"(d[31]),
      "+f"(d[32]), "+f"(d[33]), "+f"(d[34]), "+f"(d[35]), "+f"(d[36]), "+f"(d[37]), "+f"(d[38]), "+f"(d[39])
    : "r"(a0), "r"(a1), "r"(a2), "r"(a3), "l"(db), "r"(scale_d));
}

__device__ __forceinline__ void wgmma_rz_n80_b0(float* d, uint32_t a0, uint32_t a1, uint32_t a2, uint32_t a3, uint64_t db) {
  asm volatile("{\n.reg .pred p;\nsetp.ne.b32 p, 0, 0;\n"
    "wgmma.mma_async.sync.aligned.m64n80k16.f32.bf16.bf16 "
    "{%0,%1,%2,%3,%4,%5,%6,%7,%8,%9,%10,%11,%12,%13,%14,%15,%16,%17,%18,%19,%20,%21,%22,%23,%24,%25,%26,%27,%28,%29,%30,%31,%32,%33,%34,%35,%36,%37,%38,%39}, {%40,%41,%42,%43}, %44, p, 1, 1, 0;\n}\n"
    : "=f"(d[0]), "=f"(d[1]), "=f"(d[2]), "=f"(d[3]), "=f"(d[4]), "=f"(d[5]), "=f"(d[6]), "=f"(d[7]),
      "=f"(d[8]), "=f"(d[9]), "=f"(d[10]), "=f"(d[11]), "=f"(d[12]), "=f"(d[13]), "=f"(d[14]), "=f"(d[15]),
      "=f"(d[16]), "=f"(d[17]), "=f"(d[18]), "=f"(d[19]), "=f"(d[20]), "=f"(d[21]), "=f"(d[22]), "=f"(d[23]),
      "=f"(d[24]), "=f"(d[25]), "=f"(d[26]), "=f"(d[27]), "=f"(d[28]), "=f"(d[29]), "=f"(d[30]), "=f"(d[31]),
      "=f"(d[32]), "=f"(d[33]), "=f"(d[34]), "=f"(d[35]), "=f"(d[36]), "=f"(d[37]), "=f"(d[38]), "=f"(d[39])
    : "r"(a0), "r"(a1), "r"(a2), "r"(a3), "l"(db));
}

__device__ __forceinline__ void wgmma_ss_n64_a1_b1(float* d, uint64_t da, uint64_t db, int scale_d) {
  asm volatile("{\n.reg .pred p;\nsetp.ne.b32 p, %34, 0;\n"
    "wgmma.mma_async.sync.aligned.m64n64k16.f32.bf16.bf16 "
    "{%0,%1,%2,%3,%4,%5,%6,%7,%8,%9,%10,%11,%12,%13,%14,%15,%16,%17,%18,%19,%20,%21,%22,%23,%24,%25,%26,%27,%28,%29,%30,%31}, %32, %33, p, 1, 1, 1, 1;\n}\n"
    : "+f"(d[0]), "+f"(d[1]), "+f"(d[2]), "+f"(d[3]), "+f"(d[4]), "+f"(d[5]), "+f"(d[6]), "+f"(d[7]),
      "+f"(d[8]), "+f"(d[9]), "+f"(d[10]), "+f"(d[11]), "+f"(d[12]), "+f"(d[13]), "+f"(d[14]), "+f"(d[15]),
      "+f"(d[16]), "+f"(d[17]), "+f"(d[18]), "+f"(d[19]), "+f"(d[20]), "+f"(d[21]), "+f"(d[22]), "+f"(d[23]),
      "+f"(d[24]), "+f"(d[25]), "+f"(d[26]), "+f"(d[27]), "+f"(d[28]), "+f"(d[29]), "+f"(d[30]), "+f"(d[31])
    : "l"(da), "l"(db), "r"(scale_d));
}

__device__ __forceinline__ void wgmma_ss_n32_a1_b1(float* d, uint64_t da, uint64_t db, int scale_d) {
  asm volatile("{\n.reg .pred p;\nsetp.ne.b32 p, %18, 0;\n"
    "wgmma.mma_async.sync.aligned.m64n32k16.f32.bf16.bf16 "
    "{%0,%1,%2,%3,%4,%5,%6,%7,%8,%9,%10,%11,%12,%13,%14,%15}, %16, %17, p, 1, 1, 1, 1;\n}\n"
    : "+f"(d[0]), "+f"(d[1]), "+f"(d[2]), "+f"(d[3]), "+f"(d[4]), "+f"(d[5]), "+f"(d[6]), "+f"(d[7]),
      "+f"(d[8]), "+f"(d[9]), "+f"(d[10]), "+f"(d[11]), "+f"(d[12]), "+f"(d[13]), "+f"(d[14]), "+f"(d[15])
    : "l"(da), "l"(db), "r"(scale_d));
}

__device__ __forceinline__ void wgmma_ss_n144_a0_b1(float* d, uint64_t da, uint64_t db, int scale_d) {
  asm volatile("{\n.reg .pred p;\nsetp.ne.b32 p, %74, 0;\n"
    "wgmma.mma_async.sync.aligned.m64n144k16.f32.bf16.bf16 "
    "{%0,%1,%2,%3,%4,%5,%6,%7,%8,%9,%10,%11,%12,%13,%14,%15,%16,%17,%18,%19,%20,%21,%22,%23,%24,%25,%26,%27,%28,%29,%30,%31,%32,%33,%34,%35,%36,%37,%38,%39,%40,%41,%42,%43,%44,%45,%46,%47,%48,%49,%50,%51,%52,%53,%54,%55,%56,%57,%58,%59,%60,%61,%62,%63,%64,%65,%66,%67,%68,%69,%70,%71}, %72, %73, p, 1, 1, 0, 1;\n}\n"
    : "+f"(d[0]), "+f"(d[1]), "+f"(d[2]), "+f"(d[3]), "+f"(d[4]), "+f"(d[5]), "+f"(d[6]), "+f"(d[7]),
      "+f"(d[8]), "+f"(d[9]), "+f"(d[10]), "+f"(d[11]), "+f"(d[12]), "+f"(d[13]), "+f"(d[14]), "+f"(d[15]),
      "+f"(d[16]), "+f"(d[17]), "+f"(d[18]), "+f"(d[19]), "+f"(d[20]), "+f"(d[21]), "+f"(d[22]), "+f"(d[23]),
      "+f"(d[24]), "+f"(d[25]), "+f"(d[26]), "+f"(d[27]), "+f"(d[28]), "+f"(d[29]), "+f"(d[30]), "+f"(d[31]),
      "+f"(d[32]), "+f"(d[33]), "+f"(d[34]), "+f"(d[35]), "+f"(d[36]), "+f"(d[37]), "+f"(d[38]), "+f"(d[39]),
      "+f"(d[40]), "+f"(d[41]), "+f"(d[42]), "+f"(d[43]), "+f"(d[44]), "+f"(d[45]), "+f"(d[46]), "+f"(d[47]),
      "+f"(d[48]), "+f"(d[49]), "+f"(d[50]), "+f"(d[51]), "+f"(d[52]), "+f"(d[53]), "+f"(d[54]), "+f"(d[55]),
      "+f"(d[56]), "+f"(d[57]), "+f"(d[58]), "+f"(d[59]), "+f"(d[60]), "+f"(d[61]), "+f"(d[62]), "+f"(d[63]),
      "+f"(d[64]), "+f"(d[65]), "+f"(d[66]), "+f"(d[67]), "+f"(d[68]), "+f"(d[69]), "+f"(d[70]), "+f"(d[71])
    : "l"(da), "l"(db), "r"(scale_d));
}

constexpr float LOG2E = 1.4426950408889634f;

__device__ __forceinline__ float phi(float t) {
  float e = ex2(t * LOG2E);
  return (t > 0.f ? t + 1.f : e) + 1e-6f;
}

__device__ __forceinline__ void p1_slot(int it, int& buf, int& uses) {
  if (it < 9) { buf = it & 3; uses = it >> 2; }
  else { const int k = it - 9, k3 = k / 3; buf = k - 3 * k3 + 1; if (buf == 3) buf = 0; uses = (buf == 0 ? 3 : 2) + k3; }
}
template <int MODE>
__device__ __forceinline__ void p1_mainloop(float* d, int cw, uint32_t sb, int& it) {
  const uint32_t bars = sb + SM_BAR;
  int prev = 0;
#pragma unroll 1
  for (int ks = 0; ks < 9; ks++, it++) {
    int s, uses;
    p1_slot(it, s, uses);
    mbar_wait(bars + 8 * (B_FULL + s), uses & 1);
    if (it == 0) TC(1);
    TC(44 + it);
    const uint32_t base = sb + s * STAGE_BYTES;
    const uint64_t da = make_desc(base + cw * 8192, 16, 1024, 1);
    const uint64_t db = MODE ? make_desc(base + 16384, 8192, 1024, 1) : make_desc(base + 16384, 128, 1024, 0);
    wg_fence();
#pragma unroll
    for (int kk = 0; kk < 4; kk++) {
      if (MODE == 4) wgmma_ss_n256_a0_b1(d, da + kk * 2, db + kk * 128, (ks | kk) != 0);
      else if (MODE == 3) wgmma_ss_n192_a0_b1(d, da + kk * 2, db + kk * 128, (ks | kk) != 0);
      else wgmma_ss_n216_a0_b1(d, da + kk * 2, db + kk * 16, (ks | kk) != 0);
    }
    wg_commit();
    if (ks > 0) {
      wg_wait<1>();
      if (threadIdx.x % 128 == 0) mbar_arrive(bars + 8 * (B_EMPTY + prev));
    }
    prev = s;
  }
  wg_wait<0>();
  if (threadIdx.x == 0) TX(MODE ? 5 : 9);
  fence_regs<MODE ? MODE * 32 : 108>(d);
  if (threadIdx.x % 128 == 0) mbar_arrive(bars + 8 * (B_EMPTY + prev));
}

constexpr float ATT_SC = 0.23570226039551584f * LOG2E;
template <int NA, bool QSCALE>
__device__ __forceinline__ void p1_epilogue_a(const float* d, uint32_t stg) {
  const int lane = threadIdx.x % 32, w = (threadIdx.x / 32) % 4;
  const uint32_t addr = stg + ((lane >> 4) & 1) * 1024 + (w * 16 + (lane & 15)) * 16;
#pragma unroll
  for (int n = 0; n < NA * 8; n += 2) {
    const float* p = d + n * 4;
    const float sc = (QSCALE && n < 24) ? ATT_SC : 1.f;
    if (QSCALE && n < 24)
      stmatrix_x4(addr + n * 1024, pack_bf16(p[0] * sc, p[1] * sc), pack_bf16(p[2] * sc, p[3] * sc), pack_bf16(p[4] * sc, p[5] * sc), pack_bf16(p[6] * sc, p[7] * sc));
    else
      stmatrix_x4(addr + n * 1024, pack_bf16(p[0], p[1]), pack_bf16(p[2], p[3]), pack_bf16(p[4], p[5]), pack_bf16(p[6], p[7]));
  }
}

__device__ __forceinline__ void p1_epilogue_b_kv(const float* d, uint32_t sb, int cw) {
  const int lane = threadIdx.x % 32, w = (threadIdx.x / 32) % 4;
  const uint32_t row = (cw * 64 + w * 16 + (lane & 15)) * 16;
  const int hi = (lane >> 4) & 1;
#pragma unroll
  for (int n = 9; n < 27; n += 2) {
    const int c0 = n, c1 = n + 1;
    const uint32_t a0 = (c0 < 18 ? SM_PK + (c0 - 9) * 2048 : SM_V + (c0 - 18) * 2048);
    const uint32_t a1 = (c1 < 18 ? SM_PK + (c1 - 9) * 2048 : SM_V + (c1 - 18) * 2048);
    const float* p = d + n * 4;
    stmatrix_x4(sb + row + (hi ? a1 : a0), pack_bf16(p[0], p[1]), pack_bf16(p[2], p[3]), pack_bf16(p[4], p[5]), pack_bf16(p[6], p[7]));
  }
}
__device__ __forceinline__ void p1_epilogue_b_q(const float* d, uint32_t sb, int cw) {
  const int lane = threadIdx.x % 32, w = (threadIdx.x / 32) % 4;
  const uint32_t row = (cw * 64 + w * 16 + (lane & 15)) * 16;
  const int hi = (lane >> 4) & 1;
#pragma unroll
  for (int n = 0; n < 8; n += 2) {
    const float* p = d + n * 4;
    stmatrix_x4(sb + row + SM_PQ + (n + hi) * 2048, pack_bf16(p[0], p[1]), pack_bf16(p[2], p[3]), pack_bf16(p[4], p[5]), pack_bf16(p[6], p[7]));
  }
  asm volatile("stmatrix.sync.aligned.m8n8.x2.shared.b16 [%0], {%1, %2};" ::"r"(sb + row + SM_PQ + 8 * 2048), "r"(pack_bf16(d[32], d[33])), "r"(pack_bf16(d[34], d[35])) : "memory");
}

template <int MODE>
__device__ __forceinline__ void p1_produce(const CUtensorMap* mx, const CUtensorMap* mw, int rb, int c2, uint32_t sb, int& it, int nks,
                                           const CUtensorMap* mwx, int ax) {
  const uint32_t bars = sb + SM_BAR;
#pragma unroll 1
  for (int ks = 0; ks < nks; ks++, it++) {
    int s, uses;
    p1_slot(it, s, uses);
    const int kk = it < 9 ? it : it - 9;
    mbar_wait(bars + 8 * (B_EMPTY + s), (uses & 1) ^ 1);
    const uint32_t bar = bars + 8 * (B_FULL + s);
    const uint32_t dst = sb + s * STAGE_BYTES;
    mbar_expect_tx(bar, 16384 + (MODE ? MODE * 8192 + (ax >= 0 ? 8192 : 0) : 27648));
    tma_load_2d(dst, mx, bar, kk * 64, rb * 128);
    tma_load_3d(dst + 16384, mw, bar, 0, MODE ? kk * 64 : kk * 8, c2);
    if (MODE && ax >= 0) tma_load_3d(dst + 16384 + MODE * 8192, mwx, bar, 0, kk * 64, ax);
  }
}

struct QFrag { uint32_t a0, a1, a2, a3, b0, b1; };

__device__ __forceinline__ QFrag load_q(int chunk0, int off, int q0) {
  const int lane = threadIdx.x % 32, w = (threadIdx.x / 32) % 4;
  const int g = lane >> 2, t4 = lane & 3;
  const uint32_t* p = reinterpret_cast<const uint32_t*>(g_qkvA) + ((size_t)chunk0 * SEQ + q0 + w * 16 + g) * 4 + t4;
  constexpr size_t CH = (size_t)SEQ * 4;
  QFrag q;
  const int c = 2 * t4;
  const bool v0 = c >= off;
  const bool v2 = 16 + c < off + 18;
  const uint32_t z0 = (off == 6 && t4 == 0) ? 0x00003f80u : 0u;
  const uint32_t z2 = (off != 6 && t4 == 3) ? 0x3f800000u : 0u;
  q.a0 = v0 ? __ldcg(p) : z0;
  q.a1 = v0 ? __ldcg(p + 32) : z0;
  q.a2 = __ldcg(p + CH);
  q.a3 = __ldcg(p + CH + 32);
  q.b0 = v2 ? __ldcg(p + 2 * CH) : z2;
  q.b1 = v2 ? __ldcg(p + 2 * CH + 32) : z2;
  return q;
}

__device__ __forceinline__ void unpack8(const uint4 v, float* f) {
  f[0] = __uint_as_float(v.x << 16); f[1] = __uint_as_float(v.x & 0xffff0000u);
  f[2] = __uint_as_float(v.y << 16); f[3] = __uint_as_float(v.y & 0xffff0000u);
  f[4] = __uint_as_float(v.z << 16); f[5] = __uint_as_float(v.z & 0xffff0000u);
  f[6] = __uint_as_float(v.w << 16); f[7] = __uint_as_float(v.w & 0xffff0000u);
}
__device__ __forceinline__ bool attn_store_chk(const float* o, int chunk0, int off, int q0, bool doit) {
  const int lane = threadIdx.x % 32, w = (threadIdx.x / 32) % 4;
  const int g = lane >> 2, t4 = lane & 3;
  const int src = (lane & ~3) | (off == 6 ? 0 : 3);
  const float l0 = __shfl_sync(0xffffffffu, off == 6 ? o[0] : o[9], src);
  const float l1 = __shfl_sync(0xffffffffu, off == 6 ? o[2] : o[11], src);
  const bool safe = l0 >= 0x1p-90f && l0 <= 0x1p110f && l1 >= 0x1p-90f && l1 <= 0x1p110f;
  const float i0 = rcp_fast(l0), i1 = rcp_fast(l1);
  uint32_t* op = reinterpret_cast<uint32_t*>(g_oA) + ((size_t)chunk0 * SEQ + q0 + w * 16 + g) * 4 + t4;
  constexpr size_t CH = (size_t)SEQ * 4;
  const int c = 2 * t4;
  const uint32_t r0 = pack_bf16(o[0] * i0, o[1] * i0), r1 = pack_bf16(o[2] * i1, o[3] * i1);
  const uint32_t r2 = pack_bf16(o[4] * i0, o[5] * i0), r3 = pack_bf16(o[6] * i1, o[7] * i1);
  const uint32_t r4 = pack_bf16(o[8] * i0, o[9] * i0), r5 = pack_bf16(o[10] * i1, o[11] * i1);
  const bool v0 = doit && c >= off, v2 = doit && 16 + c < off + 18;
  if (v0) op[0] = r0;
  if (v0) op[32] = r1;
  if (doit) op[CH] = r2;
  if (doit) op[CH + 32] = r3;
  if (v2) op[2 * CH] = r4;
  if (v2) op[2 * CH + 32] = r5;
  return doit && !safe;
}

__device__ __forceinline__ void named_arrive(int id, int n) { asm volatile("bar.arrive %0, %1;" ::"r"(id), "r"(n) : "memory"); }
__device__ __forceinline__ void ldsm_x4(uint32_t addr, uint32_t* r) {
  asm volatile("ldmatrix.sync.aligned.m8n8.x4.shared.b16 {%0, %1, %2, %3}, [%4];" : "=r"(r[0]), "=r"(r[1]), "=r"(r[2]), "=r"(r[3]) : "r"(addr));
}
__device__ __forceinline__ void ldsm_x4_t(uint32_t addr, uint32_t* r) {
  asm volatile("ldmatrix.sync.aligned.m8n8.x4.trans.shared.b16 {%0, %1, %2, %3}, [%4];" : "=r"(r[0]), "=r"(r[1]), "=r"(r[2]), "=r"(r[3]) : "r"(addr));
}
__device__ __forceinline__ void mma16816(float* d, uint32_t a0, uint32_t a1, uint32_t a2, uint32_t a3, uint32_t b0, uint32_t b1) {
  asm("mma.sync.aligned.m16n8k16.row.col.f32.bf16.bf16.f32 {%0, %1, %2, %3}, {%4, %5, %6, %7}, {%8, %9}, {%0, %1, %2, %3};"
      : "+f"(d[0]), "+f"(d[1]), "+f"(d[2]), "+f"(d[3]) : "r"(a0), "r"(a1), "r"(a2), "r"(a3), "r"(b0), "r"(b1));
}
__device__ __forceinline__ void mma16816_z(float* d, uint32_t a0, uint32_t a1, uint32_t a2, uint32_t a3, uint32_t b0, uint32_t b1) {
  asm("mma.sync.aligned.m16n8k16.row.col.f32.bf16.bf16.f32 {%0, %1, %2, %3}, {%4, %5, %6, %7}, {%8, %9}, {%10, %10, %10, %10};"
      : "=f"(d[0]), "=f"(d[1]), "=f"(d[2]), "=f"(d[3]) : "r"(a0), "r"(a1), "r"(a2), "r"(a3), "r"(b0), "r"(b1), "f"(0.f));
}
__device__ __forceinline__ void mma1688(float* d, uint32_t a0, uint32_t a1, uint32_t b0) {
  asm("mma.sync.aligned.m16n8k8.row.col.f32.bf16.bf16.f32 {%0, %1, %2, %3}, {%4, %5}, {%6}, {%0, %1, %2, %3};"
      : "+f"(d[0]), "+f"(d[1]), "+f"(d[2]), "+f"(d[3]) : "r"(a0), "r"(a1), "r"(b0));
}
template <int MASK>
__device__ __forceinline__ void kstep_probs(const float* sa, const float* sb_, uint32_t* p, uint32_t m01) {
  p[0] = pack_bf16(ex2(sa[0]), ex2(sa[1]));
  p[1] = pack_bf16(ex2(sa[2]), ex2(sa[3]));
  p[2] = pack_bf16(ex2(sb_[0]), ex2(sb_[1]));
  p[3] = pack_bf16(ex2(sb_[2]), ex2(sb_[3]));
  if (MASK == 1) { p[0] &= m01; p[1] = 0u; p[3] &= m01; }
  if (MASK == 2) { p[0] &= ~m01; p[2] = 0u; p[3] &= ~m01; }
}
template <int MASK>
__device__ __forceinline__ void tile_kstep(float* o, const QFrag& q, const uint32_t* kf, uint32_t kc0, uint32_t kc1,
                                           const uint32_t* vf, uint32_t vc0, uint32_t vc1, uint32_t m01) {
  float s0[4], s1[4];
  mma16816_z(s0, q.a0, q.a1, q.a2, q.a3, kf[0], kf[1]);
  mma16816_z(s1, q.a0, q.a1, q.a2, q.a3, kf[2], kf[3]);
  mma1688(s0, q.b0, q.b1, kc0);
  mma1688(s1, q.b0, q.b1, kc1);
  uint32_t p[4];
  kstep_probs<MASK>(s0, s1, p, m01);
  mma16816(o, p[0], p[1], p[2], p[3], vf[0], vf[1]);
  mma16816(o + 4, p[0], p[1], p[2], p[3], vf[2], vf[3]);
  mma16816(o + 8, p[0], p[1], p[2], p[3], vc0, vc1);
}
struct KVFrag { uint32_t ka[4], kb[4], kc[4], va[4], vb[4], vc[4]; };
__device__ __forceinline__ void kv_load(KVFrag& f, uint32_t k1, uint32_t k3, uint32_t v1, uint32_t v3) {
  ldsm_x4(k1, f.ka);
  ldsm_x4(k1 + 256, f.kb);
  ldsm_x4(k3, f.kc);
  ldsm_x4_t(v1, f.va);
  ldsm_x4_t(v1 + 256, f.vb);
  ldsm_x4_t(v3, f.vc);
}
template <int MASK0, bool BOTH, int MASK1>
__device__ __forceinline__ void kstep_pair(float* o, const QFrag& q, const KVFrag& f, uint32_t m01) {
  tile_kstep<MASK0>(o, q, f.ka, f.kc[0], f.kc[1], f.va, f.vc[0], f.vc[1], m01);
  if (BOTH) tile_kstep<MASK1>(o, q, f.kb, f.kc[2], f.kc[3], f.vb, f.vc[2], f.vc[3], m01);
}

__device__ __forceinline__ QFrag load_q16(int chunk0, int off, int row0) { return load_q(chunk0, off, row0 - 16 * ((threadIdx.x / 32) % 4)); }

__device__ __forceinline__ void attn_unit_exact(const uint8_t* smem, int u) {
  const int r = fresh_tid() & 31;
  const int c2 = fresh_cta();
  const int chunk0 = ((c2 >> 2) * 18) >> 3, off = 2 * ((c2 >> 2) & 3);
  if (r < 16) {
    const int row = (c2 & 3) * 512 + u * 16 + r;
    float q[24];
#pragma unroll
    for (int c = 0; c < 3; c++) unpack8(__ldcg(reinterpret_cast<const uint4*>(g_qkvA) + (size_t)(chunk0 + c) * SEQ + row), q + c * 8);
#pragma unroll
    for (int c = 0; c < 24; c++) if (c < off || c >= off + 18) q[c] = 0.f;
    const int kl = u * 16 + r + 256;
    const int k0 = max(kl - 255, 256 - (c2 & 3) * 512), k1 = kl;
    const uint8_t* kp = smem + SM_KV;
    float m = -INFINITY;
#pragma unroll 1
    for (int k = k0; k <= k1; k++) {
      float f[24], sc = 0.f;
#pragma unroll
      for (int c = 0; c < 3; c++) unpack8(*reinterpret_cast<const uint4*>(kp + c * KV_CHUNK + k * 16), f + c * 8);
#pragma unroll
      for (int c = 0; c < 24; c++) sc = fmaf(q[c], f[c], sc);
      m = fmaxf(m, sc);
    }
    float o[24], l = 0.f;
#pragma unroll
    for (int c = 0; c < 24; c++) o[c] = 0.f;
#pragma unroll 1
    for (int k = k0; k <= k1; k++) {
      float f[24], sc = 0.f;
#pragma unroll
      for (int c = 0; c < 3; c++) unpack8(*reinterpret_cast<const uint4*>(kp + c * KV_CHUNK + k * 16), f + c * 8);
#pragma unroll
      for (int c = 0; c < 24; c++) sc = fmaf(q[c], f[c], sc);
      const float p = ex2(sc - m);
      l += p;
#pragma unroll
      for (int c = 0; c < 3; c++) unpack8(*reinterpret_cast<const uint4*>(kp + (3 + c) * KV_CHUNK + k * 16), f + c * 8);
#pragma unroll
      for (int c = 0; c < 24; c++) o[c] = fmaf(p, f[c], o[c]);
    }
    const float inv = 1.f / l;
    __nv_bfloat16* op = g_oA + ((size_t)chunk0 * SEQ + row) * 8;
#pragma unroll
    for (int c = 0; c < 24; c++)
      if (c >= off && c < off + 18) op[(size_t)(c >> 3) * SEQ * 8 + (c & 7)] = __float2bfloat16(o[c] * inv);
  }
  __syncwarp();
}

__device__ __forceinline__ void attn_loop(uint32_t sb, const uint8_t* smem, int u, QFrag q) {
  const int lane = threadIdx.x % 32;
  const int u0 = (lane >> 2) - 2 * (lane & 3);
  const uint32_t m01 = (0 > u0 ? 0x0000ffffu : 0u) | (1 > u0 ? 0xffff0000u : 0u);
  const int c2 = fresh_cta();
  const int chunk0 = ((c2 >> 2) * 18) >> 3, off = 2 * ((c2 >> 2) & 3);
  const int rbase = (c2 & 3) * 512;
  const int m = lane >> 3, r = lane & 7;
  const uint32_t kb = sb + SM_KV;
  const uint32_t ok1 = kb + (m & 1) * KV_CHUNK + ((m >> 1) * 8 + r) * 16, ok3 = kb + 2 * KV_CHUNK + lane * 16;
  const uint32_t ov1 = kb + 3 * KV_CHUNK + (m >> 1) * KV_CHUNK + ((m & 1) * 8 + r) * 16, ov3 = kb + 5 * KV_CHUNK + lane * 16;
  const int wrow = 16 * ((threadIdx.x / 32) % 4);
#pragma unroll 1
  for (;;) {
    const int un = u + 8;
    const QFrag qn = load_q16(chunk0, off, rbase + (un & 31) * 16);
    const uint32_t kw = u * 256;
    float o[12];
#pragma unroll
    for (int k = 0; k < 12; k++) o[k] = 0.f;
    KVFrag fa, fb;
    kv_load(fa, ok1 + kw, ok3 + kw, ov1 + kw, ov3 + kw);
    kv_load(fb, ok1 + kw + 512, ok3 + kw + 512, ov1 + kw + 512, ov3 + kw + 512);
    kstep_pair<1, true, 0>(o, q, fa, m01);
_Pragma(ATT_PRAGMA)
    for (int pr = 1; pr < 7; pr += 2) {
      kv_load(fa, ok1 + kw + (pr + 1) * 512, ok3 + kw + (pr + 1) * 512, ov1 + kw + (pr + 1) * 512, ov3 + kw + (pr + 1) * 512);
      kstep_pair<0, true, 0>(o, q, fb, m01);
      kv_load(fb, ok1 + kw + (pr + 2) * 512, ok3 + kw + (pr + 2) * 512, ov1 + kw + (pr + 2) * 512, ov3 + kw + (pr + 2) * 512);
      kstep_pair<0, true, 0>(o, q, fa, m01);
    }
    kv_load(fa, ok1 + kw + 8 * 512, ok3 + kw + 8 * 512, ov1 + kw + 8 * 512, ov3 + kw + 8 * 512);
    kstep_pair<0, true, 0>(o, q, fb, m01);
    kstep_pair<2, false, 0>(o, q, fa, m01);
    const bool unsafe = attn_store_chk(o, chunk0, off, rbase + u * 16 - wrow, true);
    if (__any_sync(0xffffffffu, unsafe)) attn_unit_exact(smem, u);
    if (threadIdx.x == 0) TX(38 + (u >> 3));
    if (un >= 32) break;
    u = un;
    q = qn;
  }
}

template <int POS>
__device__ __forceinline__ void kstep_pair32(float* o0, float* o1, const QFrag& q0, const QFrag& q1, const KVFrag& f, uint32_t m01) {
  tile_kstep<POS == 0 ? 1 : (POS == 2 ? 2 : 0)>(o0, q0, f.ka, f.kc[0], f.kc[1], f.va, f.vc[0], f.vc[1], m01);
  if (POS > 0) tile_kstep<0>(o1, q1, f.ka, f.kc[0], f.kc[1], f.va, f.vc[0], f.vc[1], m01);
  if (POS < 2) tile_kstep<0>(o0, q0, f.kb, f.kc[2], f.kc[3], f.vb, f.vc[2], f.vc[3], m01);
  tile_kstep<POS == 0 ? 1 : (POS == 2 ? 2 : 0)>(o1, q1, f.kb, f.kc[2], f.kc[3], f.vb, f.vc[2], f.vc[3], m01);
}
__device__ __forceinline__ void attn_loop32(uint32_t sb, const uint8_t* smem, int u, QFrag qa, QFrag qb) {
  const int lane = threadIdx.x % 32;
  const int u0 = (lane >> 2) - 2 * (lane & 3);
  const uint32_t m01 = (0 > u0 ? 0x0000ffffu : 0u) | (1 > u0 ? 0xffff0000u : 0u);
  const int c2 = fresh_cta();
  const int chunk0 = ((c2 >> 2) * 18) >> 3, off = 2 * ((c2 >> 2) & 3);
  const int rbase = (c2 & 3) * 512;
  const int m = lane >> 3, r = lane & 7;
  const uint32_t kb = sb + SM_KV;
  const uint32_t ok1 = kb + (m & 1) * KV_CHUNK + ((m >> 1) * 8 + r) * 16, ok3 = kb + 2 * KV_CHUNK + lane * 16;
  const uint32_t ov1 = kb + 3 * KV_CHUNK + (m >> 1) * KV_CHUNK + ((m & 1) * 8 + r) * 16, ov3 = kb + 5 * KV_CHUNK + lane * 16;
  const int wrow = 16 * ((threadIdx.x / 32) % 4);
#pragma unroll 1
  for (;;) {
    const int un = u + 8;
    const uint32_t kw = u * 512;
    float o0[12], o1[12];
#pragma unroll
    for (int k = 0; k < 12; k++) { o0[k] = 0.f; o1[k] = 0.f; }
    KVFrag fa, fb;
    kv_load(fa, ok1 + kw, ok3 + kw, ov1 + kw, ov3 + kw);
    kv_load(fb, ok1 + kw + 512, ok3 + kw + 512, ov1 + kw + 512, ov3 + kw + 512);
    kstep_pair32<0>(o0, o1, qa, qb, fa, m01);
#pragma unroll 1
    for (int pr = 1; pr < 7; pr += 2) {
      kv_load(fa, ok1 + kw + (pr + 1) * 512, ok3 + kw + (pr + 1) * 512, ov1 + kw + (pr + 1) * 512, ov3 + kw + (pr + 1) * 512);
      kstep_pair32<1>(o0, o1, qa, qb, fb, m01);
      kv_load(fb, ok1 + kw + (pr + 2) * 512, ok3 + kw + (pr + 2) * 512, ov1 + kw + (pr + 2) * 512, ov3 + kw + (pr + 2) * 512);
      kstep_pair32<1>(o0, o1, qa, qb, fa, m01);
    }
    kv_load(fa, ok1 + kw + 8 * 512, ok3 + kw + 8 * 512, ov1 + kw + 8 * 512, ov3 + kw + 8 * 512);
    const int rn = rbase + (un & 15) * 32;
    const QFrag qan = load_q16(chunk0, off, rn), qbn = load_q16(chunk0, off, rn + 16);
    kstep_pair32<1>(o0, o1, qa, qb, fb, m01);
    kstep_pair32<2>(o0, o1, qa, qb, fa, m01);
    const bool un0 = attn_store_chk(o0, chunk0, off, rbase + u * 32 - wrow, true);
    const bool un1 = attn_store_chk(o1, chunk0, off, rbase + u * 32 + 16 - wrow, true);
    if (__any_sync(0xffffffffu, un0)) attn_unit_exact(smem, 2 * u);
    if (__any_sync(0xffffffffu, un1)) attn_unit_exact(smem, 2 * u + 1);
    if (threadIdx.x == 0) TX(38 + (u >> 3));
    if (un >= 16) break;
    u = un;
    qa = qan;
    qb = qbn;
  }
}

__device__ __forceinline__ void kv_step(uint32_t sb, uint8_t* smem) {
  const int tid = fresh_tid();
  const int lane = tid % 32, w = (tid / 32) % 4;
  const int g = lane >> 2, t4 = lane & 3;
  float d[32], e[16];
  wg_fence();
  {
    const uint64_t da = make_desc(sb + SM_PK, 128, 2048, 0);
    const uint64_t db = make_desc(sb + SM_ONES0, 128, 2048, 0);
#pragma unroll
    for (int ks = 0; ks < 8; ks++) wgmma_ss_n64_a1_b1(d, da + ks * 16, db + ks * 16, ks != 0);
  }
  {
    const uint64_t da = make_desc(sb + SM_PK + 2048, 128, 2048, 0);
    const uint64_t db = make_desc(sb + SM_V + 6 * 2048, 128, 2048, 0);
#pragma unroll
    for (int ks = 0; ks < 8; ks++) wgmma_ss_n32_a1_b1(e, da + ks * 16, db + ks * 16, ks != 0);
  }
  wg_commit();
  wg_wait<0>();
  fence_regs<32>(d);
  fence_regs<16>(e);
  float* dst = reinterpret_cast<float*>(smem + SM_KVP);
#pragma unroll
  for (int hh = 0; hh < 2; hh++) {
    const int f = 16 * w + g + 8 * hh;
    const int base = 18 * (f / 18);
    const bool ok = f < 54;
    if (ok && t4 == 0) { dst[f * 20 + 18] = d[2 * hh]; dst[f * 20 + 19] = 0.f; }
#pragma unroll
    for (int n = 1; n < 8; n++) {
      const int c = 8 * (n - 1) + 2 * t4 - base;
      if (ok && c >= 0 && c < 18) *reinterpret_cast<float2*>(dst + f * 20 + c) = make_float2(d[n * 4 + hh * 2], d[n * 4 + hh * 2 + 1]);
    }
    const int f2 = f + 8;
    const bool ok2 = f2 >= 54;
    if (ok2 && t4 == 0) { dst[f2 * 20 + 18] = e[12 + 2 * hh]; dst[f2 * 20 + 19] = 0.f; }
#pragma unroll
    for (int n = 0; n < 3; n++) {
      const int c = 8 * n + 2 * t4 - 6;
      if (ok2 && c >= 0) *reinterpret_cast<float2*>(dst + f2 * 20 + c) = make_float2(e[n * 4 + hh * 2], e[n * 4 + hh * 2 + 1]);
    }
  }
}

__device__ __forceinline__ uint32_t phi2(uint32_t x) {
  return pack_bf16(phi(__uint_as_float(x << 16)), phi(__uint_as_float(x & 0xffff0000u)));
}
__device__ __forceinline__ void ob_step(int cw, uint32_t sb, int grp, int rb) {
  const int tid = fresh_tid();
  const int lane = tid % 32, w = (tid / 32) % 4;
  const int g = lane >> 2, t4 = lane & 3;
  float d[40];
  uint32_t a[18];
  {
    const uint32_t qa = sb + SM_PQ + (cw * 64 + w * 16 + (lane & 15)) * 16 + ((lane >> 4) & 1) * 2048;
#pragma unroll
    for (int ks = 0; ks < 4; ks++)
      asm volatile("ldmatrix.sync.aligned.m8n8.x4.shared.b16 {%0, %1, %2, %3}, [%4];"
                   : "=r"(a[ks * 4]), "=r"(a[ks * 4 + 1]), "=r"(a[ks * 4 + 2]), "=r"(a[ks * 4 + 3]) : "r"(qa + ks * 4096));
    asm volatile("ldmatrix.sync.aligned.m8n8.x2.shared.b16 {%0, %1}, [%2];" : "=r"(a[16]), "=r"(a[17])
                 : "r"(sb + SM_PQ + (cw * 64 + w * 16 + (lane & 15)) * 16 + 8 * 2048));
#pragma unroll
    for (int i = 0; i < 18; i++) a[i] = phi2(a[i]);
  }
  const uint64_t db = make_desc(sb + SM_KVMAT, 1280, 128, 0);
  wg_fence();
  wgmma_rz_n80_b0(d, a[0], a[1], a[2], a[3], db);
#pragma unroll
  for (int ks = 1; ks < 4; ks++) wgmma_rs_n80_b0(d, a[ks * 4], a[ks * 4 + 1], a[ks * 4 + 2], a[ks * 4 + 3], db + ks * 160, 1);
  wgmma_rs_n80_b0(d, a[16], a[17], 0u, 0u, db + 4 * 160, 1);
  wg_commit();
  wg_wait<0>();
  fence_regs<40>(d);
  float inv[2][4];
#pragma unroll
  for (int hh = 0; hh < 2; hh++) {
#pragma unroll
    for (int h = 0; h < 4; h++) {
      const float dn = __shfl_sync(0xffffffffu, d[36 + 2 * hh + (h & 1)], (lane & ~3) | (h >> 1));
      inv[hh][h] = rcp_fast(dn + 1e-6f);
    }
  }
  uint32_t* op = reinterpret_cast<uint32_t*>(g_oB) + ((size_t)(grp * 9) * SEQ + rb * 128 + cw * 64 + w * 16 + g) * 4 + t4;
  constexpr size_t CH = (size_t)SEQ * 4;
#pragma unroll
  for (int n = 0; n < 9; n++) {
    const int hlo = (8 * n) / 18, hhi = (8 * n + 6) / 18;
    const bool hi = (8 * n + 2 * t4) >= 18 * hhi;
    const float a = hi ? inv[0][hhi] : inv[0][hlo];
    const float b = hi ? inv[1][hhi] : inv[1][hlo];
    op[n * CH] = pack_bf16(d[n * 4] * a, d[n * 4 + 1] * a);
    op[n * CH + 32] = pack_bf16(d[n * 4 + 2] * b, d[n * 4 + 3] * b);
  }
}

__global__ void __launch_bounds__(NTHREADS, 1) fused_kernel(const __grid_constant__ Params p) {
  extern __shared__ uint8_t smem_raw[];
  const uint32_t sb = (smem_u32(smem_raw) + 1023) & ~1023u;
  uint8_t* smem = smem_raw + (sb - smem_u32(smem_raw));
  const uint32_t bars = sb + SM_BAR;
  volatile unsigned* s_epoch = reinterpret_cast<volatile unsigned*>(smem + SM_MISC);
  const int warp = __shfl_sync(0xffffffffu, (int)(threadIdx.x / 32), 0), lane = threadIdx.x % 32;
  const int cta = blockIdx.x;
  const int rb = cta % 16, j = cta / 16;
  const int a0 = 3 * j, ax = j < 6 ? 24 + (j >> 1) : -1, axw = j & 1;
  int it_prod = 0;

  TC(0);
  if (threadIdx.x == 256) {
    TX(0);
    TL(0);
    prefetch_map(&p.xA);
    prefetch_map(&p.wA3);
    prefetch_map(&p.wA1);
    for (int i = 0; i < 4; i++) { mbar_init(bars + 8 * (B_FULL + i), 1); mbar_init(bars + 8 * (B_EMPTY + i), 2); }
    TX(1);
    asm volatile("fence.mbarrier_init.release.cluster;" ::: "memory");
    fence_async_smem();
    TX(2);
    p1_produce<3>(&p.xA, &p.wA3, rb, a0, sb, it_prod, 1, &p.wA1, ax);
    TX(3);
  } else if (threadIdx.x == 288) {
    for (int i = 0; i < 4; i++) { mbar_init(bars + 8 * (B_FULL3 + i), 1); mbar_init(bars + 8 * (B_EMPTY3 + i), 2); }
    for (int i = 0; i < 2; i++) mbar_init(bars + 8 * (B_STGA + i), 1);
    mbar_init(bars + 8 * B_KV, 1);
    mbar_init(bars + 8 * B_KV2, 96);
    mbar_init(bars + 8 * B_BLOADS, 1);
    mbar_init(bars + 8 * B_ADEP, 1);
    mbar_init(bars + 8 * B_BST, 256);
    mbar_init(bars + 8 * B_P2DONE, 128);
    mbar_init(bars + 8 * B_OA, 384);
    mbar_init(bars + 8 * B_EPOCH, 1);
    asm volatile("fence.mbarrier_init.release.cluster;" ::: "memory");
  }
  __syncthreads();
  if (threadIdx.x == 0) TX(4);
  if (warp >= 8) {
    if (warp == 8) {
      if (lane == 0) {
        int it = it_prod;
        p1_produce<3>(&p.xA, &p.wA3, rb, a0, sb, it, 8, &p.wA1, ax);
        mbar_wait(bars + 8 * B_EPOCH, 0);
        TL(20);
        cnt_wait(C_W, (*s_epoch + 1) * NCTA);
        TL(21);
        fence_async_glb();
        p1_produce<0>(&p.xB, &p.wB, rb, j * 27, sb, it, 9, nullptr, -1);
        mbar_arrive(bars + 8 * B_BLOADS);
      }
      __syncwarp();
    } else {
      const int ht = threadIdx.x - 288;
      unsigned ticket = 0;
      if (ht == 95) ticket = atomicAdd(&g_cnt[C_TICKET * 32], 1u);
      {
        uint4 v[11];
#pragma unroll
        for (int i = 0; i < 11; i++) {
          const int li = ht + i * 96;
          const int idx = cta * 972 + li;
          const int blk = idx >> 5, r = idx & 31;
          const int kg = blk / 54, cg = blk - kg * 54;
          const int k = kg * 8 + (r & 7), c = cg * 4 + (r >> 3);
          const int g = c / 27, rr = c - g * 27, part = rr / 9, cc = rr - part * 9;
          if (li < 972) v[i] = __ldg(reinterpret_cast<const uint4*>(p.wBsrc + (size_t)k * 1728 + part * 576 + g * 72 + cc * 8));
        }
        if (ht == 95) {
          *s_epoch = ticket / NCTA;
          mbar_arrive(bars + 8 * B_EPOCH);
        }
#pragma unroll
        for (int i = 0; i < 11; i++) {
          const int li = ht + i * 96;
          const int idx = cta * 972 + li;
          const int blk = idx >> 5, r = idx & 31;
          const int kg = blk / 54, cg = blk - kg * 54;
          if (li < 972) reinterpret_cast<uint4*>(g_wBp)[(size_t)(cg * 4 + (r >> 3)) * 576 + kg * 8 + (r & 7)] = v[i];
          if (PERM_GAP) pace(PERM_GAP);
        }
      }
      if (rb == 0) {
        for (int i = ht; i < 72 * 20; i += 96) g_kvsum[j * 72 * 20 + i] = 0.f;
      }
      named_bar(5, 96);
      if (ht == 32) { cnt_signal(C_W); TL(19); }
      mbar_wait(bars + 8 * B_EPOCH, 0);
      if (warp >= 10) {
        const int h2 = threadIdx.x - 320;
        uint4 u[11];
#pragma unroll
        for (int i = 0; i < 11; i++) {
          const int li = h2 + i * 64;
          const int idx = cta * 648 + li;
          const int blk = idx >> 5, r = idx & 31;
          const int mat = blk / 1296, b2 = blk - mat * 1296;
          const int kg = b2 / 18, cg = b2 - kg * 18;
          const int k = kg * 8 + (r & 7), ch = cg * 4 + (r >> 3);
          if (li < 648) u[i] = __ldg(reinterpret_cast<const uint4*>((mat ? p.woB : p.woA) + (size_t)k * 576 + ch * 8));
        }
        mbar_wait(bars + 8 * B_BLOADS, 0);
#pragma unroll
        for (int i = 0; i < 11; i++) {
          const int li = h2 + i * 64;
          const int idx = cta * 648 + li;
          const int blk = idx >> 5, r = idx & 31;
          const int mat = blk / 1296, b2 = blk - mat * 1296;
          const int kg = b2 / 18, cg = b2 - kg * 18;
          if (li < 648) reinterpret_cast<uint4*>(g_woP)[(size_t)(mat * 72 + cg * 4 + (r >> 3)) * 576 + kg * 8 + (r & 7)] = u[i];
        }
        named_bar(6, 64);
        if (h2 == 0) cnt_signal(C_W2);
      }
      if (warp == 9) {
        const int head = cta >> 2, quarter = cta & 3;
        if (lane == 0) {
          mbar_wait(bars + 8 * (B_STGA + 0), 0);
          mbar_wait(bars + 8 * (B_STGA + 1), 0);
          for (int pc = 0; pc < 6; pc++) {
            tma_store_3d(&p.st4, sb + SM_KV + pc * 4096, 0, rb * 16, a0 * 8 + pc * 4);
            tma_store_3d(&p.st4, sb + SM_KV + 32768 + pc * 4096, 0, rb * 16 + 8, a0 * 8 + pc * 4);
            bulk_commit();
            if (AST_GAP) pace(AST_GAP);
          }
          if (ax >= 0) {
            tma_store_3d(&p.st4, sb + SM_KV + axw * 32768 + 6 * 4096, 0, rb * 16 + axw * 8, ax * 8);
            tma_store_3d(&p.st4, sb + SM_KV + axw * 32768 + 7 * 4096, 0, rb * 16 + axw * 8, ax * 8 + 4);
            bulk_commit();
          }
          TX(16);
          bulk_wait_all();
          TX(17);
          cnt_signal_nofence(C_A + rb);
          TX(18);
          TL(3);
        }
        __syncwarp();
        {
          const int r = quarter * 4 - 2 + lane;
          cnt_wait_warp(C_A + (r & 15), (*s_epoch + 1) * 8, lane < 6 && r >= 0);
        }
        if (lane == 0) {
          mbar_arrive(bars + 8 * B_ADEP);
          fence_async_glb();
          TL(4);
          mbar_wait(bars + 8 * B_BLOADS, 0);
          const int chunk0 = (head * 18) >> 3;
          TX(19);
          mbar_expect_tx(bars + 8 * B_KV, 6 * KV_CHUNK);
          tma_load_3d(sb + SM_KV, &p.kvA, bars + 8 * B_KV, 0, quarter * 64 - 32, 72 + chunk0);
          tma_load_3d(sb + SM_KV + 3 * KV_CHUNK, &p.kvA, bars + 8 * B_KV, 0, quarter * 64 - 32, 144 + chunk0);
        }
        __syncwarp();
      }
      {
        const int head = cta >> 2, quarter = cta & 3;
        mbar_wait(bars + 8 * B_KV, 0);
        if (threadIdx.x == 288) TX(20);
        const int cs = (head & 3) == 3 ? 0 : 23;
        uint8_t* kp = smem + SM_KV + (cs >> 3) * KV_CHUNK + (cs & 7) * 2;
        for (int i = threadIdx.x - 288; i < 768; i += 96) {
          const bool valid = quarter * 512 - 256 + i >= 0;
          *reinterpret_cast<uint16_t*>(kp + i * 16) = valid ? (uint16_t)0 : (uint16_t)0xf14a;
          *reinterpret_cast<uint16_t*>(kp + 3 * KV_CHUNK + i * 16) = valid ? (uint16_t)0x3f80 : (uint16_t)0;
        }
        fence_async_smem();
        if (threadIdx.x == 288) TX(21);
        mbar_arrive(bars + 8 * B_KV2);
      }
    }
  } else {
    const int cw = warp >> 2;
    const bool elect = (threadIdx.x % 128) == 0;
    {
      float d[128];
      int it = 0;
      const bool has_x = ax >= 0 && axw == cw;
      if (has_x) p1_mainloop<4>(d, cw, sb, it); else p1_mainloop<3>(d, cw, sb, it);
      if (threadIdx.x == 0) TL(1);
      mbar_wait(bars + 8 * (B_EMPTY + 3), 1);
      if (j < 3) { if (has_x) p1_epilogue_a<4, true>(d, sb + SM_KV + cw * 32768); else p1_epilogue_a<3, true>(d, sb + SM_KV + cw * 32768); }
      else { if (has_x) p1_epilogue_a<4, false>(d, sb + SM_KV + cw * 32768); else p1_epilogue_a<3, false>(d, sb + SM_KV + cw * 32768); }
      if (threadIdx.x == 0) TX(6);
      fence_async_smem();
      if (threadIdx.x == 0) TX(7);
      named_bar(1 + cw, 128);
      if (elect) mbar_arrive(bars + 8 * (B_STGA + cw));
      if (threadIdx.x == 0) TX(8);
      if (threadIdx.x == 0) TL(2);
      TC(2);
      p1_mainloop<0>(d, cw, sb, it);
#pragma unroll
      for (int i = 36; i < 72; i++) d[i] = phi(d[i]);
      mbar_wait(bars + 8 * (B_EMPTY + 1), 0);
      mbar_wait(bars + 8 * (B_EMPTY + 2), 0);
      if (threadIdx.x == 0) { TL(5); TX(11); }
      p1_epilogue_b_kv(d, sb, cw);
      p1_epilogue_b_q(d, sb, cw);
      if (threadIdx.x == 0) TX(12);
      fence_async_smem();
      mbar_arrive(bars + 8 * B_BST);
      if (threadIdx.x == 0) { TL(11); TX(13); }
    }
  }
  const int warp2 = __shfl_sync(0xffffffffu, fresh_tid() >> 5, 0), lane2 = fresh_tid() & 31;
  const uint32_t sb2 = (smem_u32(smem_raw) + 1023) & ~1023u;
  uint8_t* smem2 = smem_raw + (sb2 - smem_u32(smem_raw));
  const uint32_t bars2 = sb2 + SM_BAR;
  volatile unsigned* s_epoch2 = reinterpret_cast<volatile unsigned*>(smem2 + SM_MISC);
  if (warp2 >= 8) {
    const int c3 = fresh_cta();
    const int grp = c3 >> 4;
    mbar_wait(bars2 + 8 * B_BST, 0);
    if (threadIdx.x == 256) TX(25);
    {
      const int t = fresh_tid() - 256;
      const uint4 one4 = make_uint4(0x3f803f80u, 0x3f803f80u, 0x3f803f80u, 0x3f803f80u);
      reinterpret_cast<uint4*>(smem2 + SM_ONES0)[t] = one4;
      reinterpret_cast<uint4*>(smem2 + SM_ONES1)[t] = one4;
      for (int i = t; i < 800; i += 128) reinterpret_cast<uint4*>(smem2 + SM_KVMAT)[i] = make_uint4(0, 0, 0, 0);
      fence_async_smem();
      named_bar(3, 128);
    }
    kv_step(sb2, smem2);
    fence_async_smem();
    named_bar(3, 128);
    if (threadIdx.x == 256) {
      asm volatile("cp.reduce.async.bulk.global.shared::cta.bulk_group.add.f32 [%0], [%1], %2;"
                   ::"l"(g_kvsum + grp * 72 * 20), "r"(sb2 + SM_KVP), "n"(5760) : "memory");
      bulk_commit();
      bulk_wait_all();
      cnt_signal_nofence(C_KV + grp);
      TX(29);
      cnt_wait(C_KV + grp, (*s_epoch2 + 1) * 16);
    }
    named_bar(3, 128);
    const int f = fresh_tid() - 256;
    if (f < 72) {
      const float4* src = reinterpret_cast<const float4*>(g_kvsum + (grp * 72 + f) * 20);
      float v[20];
#pragma unroll
      for (int r = 0; r < 5; r++) {
        const float4 x = __ldcg(src + r);
        v[r * 4] = x.x; v[r * 4 + 1] = x.y; v[r * 4 + 2] = x.z; v[r * 4 + 3] = x.w;
      }
      const int h2 = f / 18;
      __nv_bfloat16* km = reinterpret_cast<__nv_bfloat16*>(smem2 + SM_KVMAT) + (f >> 3) * 640 + (f & 7);
#pragma unroll
      for (int e = 0; e < 18; e++) km[(h2 * 18 + e) * 8] = __float2bfloat16(v[e]);
      km[(72 + h2) * 8] = __float2bfloat16(v[18]);
    }
    fence_async_smem();
    named_bar(3, 128);
#pragma unroll 1
    for (int hf = 0; hf < 2; hf++) ob_step(hf, sb2, grp, c3 & 15);
    if (threadIdx.x == 256) { TX(35); TL(10); }
    mbar_arrive(bars2 + 8 * B_P2DONE);
    fence_gpu();
    if ((fresh_tid() & 31) < 2)
      asm volatile("red.relaxed.gpu.global.add.u32 [%0], 1;" ::"l"(&g_cnt[(C_OB + (c3 & 15) * 9 + ((grp * 72 + (fresh_tid() & 31) * 71) >> 6)) * 32]) : "memory");
  } else {
    const int c2 = fresh_cta();
    mbar_wait(bars2 + 8 * B_ADEP, 0);
    const QFrag qa = load_q16(((c2 >> 2) * 18) >> 3, 2 * ((c2 >> 2) & 3), (c2 & 3) * 512 + warp2 * 32);
    const QFrag qb = load_q16(((c2 >> 2) * 18) >> 3, 2 * ((c2 >> 2) & 3), (c2 & 3) * 512 + warp2 * 32 + 16);
    mbar_wait(bars2 + 8 * B_KV2, 0);
    if (threadIdx.x == 0) { TL(7); TX(31); }
    attn_loop32(sb2, smem_raw + (((smem_u32(smem_raw) + 1023) & ~1023u) - smem_u32(smem_raw)), warp2, qa, qb);
  }
  const int warp3 = __shfl_sync(0xffffffffu, fresh_tid() >> 5, 0), lane3 = fresh_tid() & 31;
  const uint32_t sb3 = (smem_u32(smem_raw) + 1023) & ~1023u;
  uint8_t* smem3 = smem_raw + (sb3 - smem_u32(smem_raw));
  const uint32_t bars3 = sb3 + SM_BAR;
  volatile unsigned* s_epoch3 = reinterpret_cast<volatile unsigned*>(smem3 + SM_MISC);
  if (threadIdx.x == 0) TX(33);
  unsigned w2seen = 0;
  if (threadIdx.x == 256) w2seen = ld_relaxed(&g_cnt[C_W2 * 32]);
  fence_gpu();
  {
    const int c5 = fresh_cta();
    const int hd = c5 >> 2, k0 = (hd * 18) >> 6, k1 = (hd * 18 + 17) >> 6;
    if (warp3 < 8 && lane3 < 8 && (lane3 < 4 || k1 != k0))
      asm volatile("red.relaxed.gpu.global.add.u32 [%0], 1;" ::"l"(&g_cnt[(C_OA + ((c5 & 3) * 4 + (lane3 & 3)) * 9 + (lane3 < 4 ? k0 : k1)) * 32]) : "memory");
  }
  mbar_arrive(bars3 + 8 * B_OA);
  if (threadIdx.x == 128) TX(36);
  if (threadIdx.x == 0) TX(37);
  if (warp3 >= 8) {
    if (warp3 == 8) {
      const int c3 = fresh_cta();
      const unsigned ep = *s_epoch3 + 1;
      const int br = c3 >> 6, rb3 = (c3 >> 2) & 15, jj3 = c3 & 3;
      const CUtensorMap* mo = br ? &p.oB : &p.oA;
      const int ks = lane3 < 9 ? lane3 : 0;
      const int per = br ? 72 : 18;
      const unsigned target = ep * (unsigned)((((ks * 64 + 63) / per) - ((ks * 64) / per) + 1) * (br ? 4 : 8));
      const unsigned* cnt = &g_cnt[((br ? C_OB : C_OA) + rb3 * 9 + ks) * 32];
      if (lane3 == 0) {
        if ((int)(w2seen - ep * NCTA) < 0) cnt_wait(C_W2, ep * NCTA);
        mbar_wait(bars3 + 8 * B_P2DONE, 0);
      }
      if (lane3 == 0) {
        fence_async_glb();
        for (int k = 0; k < 4; k++) {
          const uint32_t bar = bars3 + 8 * (B_FULL3 + k);
          mbar_expect_tx(bar, WO_STAGE);
          tma_load_3d(sb3 + k * WO_STAGE + 16384, &p.wo, bar, 0, k * 8, br * 72 + jj3 * 18);
        }
      }
      __syncwarp();
      if (!br) mbar_wait(bars3 + 8 * B_OA, 0);
      unsigned ready = 0;
      int n = 0, spins = 0;
      while (n < 9 && ++spins < (1 << 20)) {
        const bool ok = lane3 < 9 && (((ready >> lane3) & 1) || (int)(ld_acquire(cnt) - target) >= 0);
        ready = __ballot_sync(0xffffffffu, ok);
        if (lane3 == 0 && ((ready >> n) & 1)) {
          fence_async_glb();
          if (n == 0) TL(12);
          while (n < 9 && ((ready >> n) & 1)) {
            const int s = n % WO_NSTAGE;
            const uint32_t bar = bars3 + 8 * (B_FULL3 + s);
            if (n >= 4) {
              mbar_wait(bars3 + 8 * (B_EMPTY3 + s), ((n / WO_NSTAGE) & 1) ^ 1);
              mbar_expect_tx(bar, WO_STAGE);
              tma_load_3d(sb3 + s * WO_STAGE + 16384, &p.wo, bar, 0, n * 8, br * 72 + jj3 * 18);
            }
            tma_load_3d(sb3 + s * WO_STAGE, mo, bar, 0, rb3 * 16, n * 8);
            n++;
          }
        }
        n = __shfl_sync(0xffffffffu, n, 0);
      }
    }
  } else {
    const int cw = warp3 >> 2;
    const bool elect = (threadIdx.x % 128) == 0;
    if (threadIdx.x == 0) TL(9);
    {
      float d[72];
#pragma unroll 1
      for (int ks = 0; ks < 9; ks++) {
        const int s = ks % WO_NSTAGE;
        mbar_wait(bars3 + 8 * (B_FULL3 + s), (ks / WO_NSTAGE) & 1);
        if (ks == 0 && threadIdx.x == 0) TL(13);
        const uint32_t base = sb3 + s * WO_STAGE;
        const uint64_t da = make_desc(base + cw * 1024, 2048, 128, 0);
        const uint64_t db = make_desc(base + 16384, 128, 1024, 0);
        wg_fence();
#pragma unroll
        for (int kk = 0; kk < 4; kk++) wgmma_ss_n144_a0_b1(d, da + kk * 256, db + kk * 16, (ks | kk) != 0);
        wg_commit();
        if (ks > 0) {
          wg_wait<1>();
          if (elect) mbar_arrive(bars3 + 8 * (B_EMPTY3 + (ks - 1) % WO_NSTAGE));
        }
      }
      wg_wait<0>();
      fence_regs<72>(d);
      if (threadIdx.x == 0) TL(14);
      mbar_wait(bars3 + 8 * B_OA, 0);
      const int w = warp3 & 3;
      const uint32_t stg = sb3 + SM_KV + cw * 18432;
      const uint32_t addr = stg + (w * 16 + (lane3 & 15)) * 288 + ((lane3 >> 4) & 1) * 16;
#pragma unroll
      for (int n = 0; n < 18; n += 2) {
        const float* q = d + n * 4;
        stmatrix_x4(addr + n * 16, pack_bf16(q[0], q[1]), pack_bf16(q[2], q[3]), pack_bf16(q[4], q[5]), pack_bf16(q[6], q[7]));
      }
      fence_async_smem();
      __syncwarp();
      if (lane3 == 0) {
        const int c4 = fresh_cta();
        tma_store_2d(&p.out, stg + w * 16 * 288, (c4 >> 6) * 576 + (c4 & 3) * 144, ((c4 >> 2) & 15) * 128 + cw * 64 + w * 16);
        bulk_commit();
        bulk_wait_read();
        if (threadIdx.x == 0) TL(15);
      }
    }
  }
}

typedef CUresult (*EncodeFn)(CUtensorMap*, CUtensorMapDataType, cuuint32_t, void*, const cuuint64_t*, const cuuint64_t*,
                             const cuuint32_t*, const cuuint32_t*, CUtensorMapInterleave, CUtensorMapSwizzle,
                             CUtensorMapL2promotion, CUtensorMapFloatOOBfill);

CUtensorMap make_map(EncodeFn fn, const void* base, int rank, const cuuint64_t* dims, const cuuint64_t* strides,
                     const cuuint32_t* box, CUtensorMapSwizzle swz) {
  CUtensorMap m;
  cuuint32_t es[5] = {1, 1, 1, 1, 1};
  fn(&m, CU_TENSOR_MAP_DATA_TYPE_BFLOAT16, rank, const_cast<void*>(base), dims, strides, box, es, CU_TENSOR_MAP_INTERLEAVE_NONE, swz,
     CU_TENSOR_MAP_L2_PROMOTION_L2_128B, CU_TENSOR_MAP_FLOAT_OOB_FILL_NONE);
  return m;
}

CUtensorMap panel_map(EncodeFn fn, const void* base, int rowgroups, int chunks, int box_rg, int box_ch) {
  cuuint64_t d[3] = {64, (cuuint64_t)rowgroups, (cuuint64_t)chunks};
  cuuint64_t s[2] = {128, (cuuint64_t)rowgroups * 128};
  cuuint32_t b[3] = {64, (cuuint32_t)box_rg, (cuuint32_t)box_ch};
  return make_map(fn, base, 3, d, s, b, CU_TENSOR_MAP_SWIZZLE_NONE);
}

}

extern "C" void kernel_launch(void* const* d_in, const int* in_sizes, int n_in, void* d_out, int out_size) {
  (void)in_sizes; (void)n_in; (void)out_size;
  static Params P;
  static const void* cached[7] = {nullptr, nullptr, nullptr, nullptr, nullptr, nullptr, nullptr};
  bool same = true;
  for (int i = 0; i < 6; i++) same = same && cached[i] == d_in[i];
  same = same && cached[6] == d_out;
  if (!same) {
    void* fnp = nullptr;
    cudaDriverEntryPointQueryResult qr;
    cudaGetDriverEntryPoint("cuTensorMapEncodeTiled", &fnp, cudaEnableDefault, &qr);
    EncodeFn fn = (EncodeFn)fnp;
    const void *xA = d_in[0], *wA = d_in[1], *woA = d_in[2], *xB = d_in[3], *wB = d_in[4], *woB = d_in[5];
    void *qkvA, *wBp, *oA, *oB, *woP;
    cudaGetSymbolAddress(&qkvA, g_qkvA);
    cudaGetSymbolAddress(&wBp, g_wBp);
    cudaGetSymbolAddress(&oA, g_oA);
    cudaGetSymbolAddress(&oB, g_oB);
    cudaGetSymbolAddress(&woP, g_woP);
    {
      cuuint64_t d[2] = {576, SEQ}, s[1] = {1152};
      cuuint32_t b[2] = {64, 128};
      P.xA = make_map(fn, xA, 2, d, s, b, CU_TENSOR_MAP_SWIZZLE_128B);
      P.xB = make_map(fn, xB, 2, d, s, b, CU_TENSOR_MAP_SWIZZLE_128B);
    }
    {
      cuuint64_t d[3] = {64, 576, 27}, s[2] = {3456, 128};
      cuuint32_t b1[3] = {64, 64, 1}, b3[3] = {64, 64, 3};
      P.wA3 = make_map(fn, wA, 3, d, s, b3, CU_TENSOR_MAP_SWIZZLE_128B);
      P.wA1 = make_map(fn, wA, 3, d, s, b1, CU_TENSOR_MAP_SWIZZLE_128B);
    }
    P.wB = panel_map(fn, wBp, 72, 216, 8, 27);
    P.st4 = panel_map(fn, qkvA, 256, 216, 8, 4);
    P.kvA = panel_map(fn, qkvA, 256, 216, 96, 3);
    P.oA = panel_map(fn, oA, 256, 72, 16, 8);
    P.oB = panel_map(fn, oB, 256, 72, 16, 8);
    P.wo = panel_map(fn, woP, 72, 144, 8, 18);
    {
      cuuint64_t d[2] = {1152, SEQ}, s[1] = {2304};
      cuuint32_t b[2] = {144, 16};
      P.out = make_map(fn, d_out, 2, d, s, b, CU_TENSOR_MAP_SWIZZLE_NONE);
    }
    P.wBsrc = (const __nv_bfloat16*)wB;
    P.xAsrc = (const __nv_bfloat16*)xA;
    P.wAsrc = (const __nv_bfloat16*)wA;
    P.woA = (const __nv_bfloat16*)woA;
    P.woB = (const __nv_bfloat16*)woB;
    cudaFuncSetAttribute(fused_kernel, cudaFuncAttributeMaxDynamicSharedMemorySize, SMEM_BYTES);
    for (int i = 0; i < 6; i++) cached[i] = d_in[i];
    cached[6] = d_out;
  }
  cudaLaunchConfig_t cfg = {};
  cfg.gridDim = dim3(NCTA);
  cfg.blockDim = dim3(NTHREADS);
  cfg.dynamicSmemBytes = SMEM_BYTES;
  cfg.stream = cudaStreamPerThread;
  cudaLaunchAttribute at[1];
  at[0].id = cudaLaunchAttributeCooperative;
  at[0].val.cooperative = 1;
  cfg.attrs = at;
  cfg.numAttrs = 1;
  cudaLaunchKernelEx(&cfg, fused_kernel, P);
}
```
